```python
import torch

def _softmax(x, axis=-1):
    return torch.softmax(x, dim=axis)
def _gelu(x):
    return torch.nn.functional.gelu(x, approximate="tanh")
def _silu(x):
    return torch.nn.functional.silu(x)
def _sigmoid(x):
    return torch.sigmoid(x)
def _layernorm(x, axis=-1, eps=1e-5):
    m = x.mean(dim=axis, keepdim=True)
    v = x.var(dim=axis, keepdim=True, unbiased=False)
    return (x - m) / torch.sqrt(v + eps)
def _scatter_add(tgt, idx, src, axis=0):
    return tgt.clone().index_add_(axis, idx, src)
def _segment_sum(src, seg, n):
    out = torch.zeros((n,) + src.shape[1:], dtype=src.dtype)
    return out.index_add_(0, seg, src)
def _pad(x, pw):
    flat = tuple(v for pair in reversed(pw) for v in pair)
    return torch.nn.functional.pad(x, flat)

kernel_name = 'gated_mix__ssm_conv_s5__dense_activation_relu__prompt'

def setup_inputs():

    _w = (lambda a: (lambda t: t.to(torch.bfloat16) if t.is_floating_point() else t)(torch.as_tensor(a)))
    def _A_setup():
        B, S, D = 1, 2048, 1024
        P = D
        Lambda_re = -0.5 * (lambda _x: torch.exp(torch.as_tensor(_x)))((lambda *s: torch.randn(*s, dtype=torch.bfloat16) * 0.8)(P))
        Lambda_im = (lambda *s: torch.randn(*s, dtype=torch.bfloat16) * 0.8)(P) * 1.0
        B_re = (lambda *s: torch.randn(*s, dtype=torch.bfloat16) * 0.8)(P, D) * (D ** -0.5)
        B_im = (lambda *s: torch.randn(*s, dtype=torch.bfloat16) * 0.8)(P, D) * (D ** -0.5)
        C_re = (lambda *s: torch.randn(*s, dtype=torch.bfloat16) * 0.8)(D, P) * (P ** -0.5)
        C_im = (lambda *s: torch.randn(*s, dtype=torch.bfloat16) * 0.8)(D, P) * (P ** -0.5)
        log_dt = (lambda *s: torch.randn(*s, dtype=torch.bfloat16) * 0.8)(P) * 0.3 - 2.0
        Dskip = (lambda *s: torch.randn(*s, dtype=torch.bfloat16) * 0.8)(D)
        return {
            "x": _w((lambda *s: torch.randn(*s, dtype=torch.bfloat16) * 0.05)(B, S, D)),
            "Lambda_re": _w(Lambda_re),
            "Lambda_im": _w(Lambda_im),
            "B_re": _w(B_re),
            "B_im": _w(B_im),
            "C_re": _w(C_re),
            "C_im": _w(C_im),
            "log_dt": _w(log_dt),
            "Dskip": _w(Dskip),
        }
    _A_in = _A_setup()

    def _B_setup():
        B, S, D, Dff = 1, 2048, 1024, 3584
        return {
            "x": _w((lambda *s: torch.randn(*s, dtype=torch.bfloat16) * 0.05)(B, S, D)),
            "w1": _w((lambda *s: torch.randn(*s, dtype=torch.bfloat16) * 0.05)(D, Dff)),
            "w2": _w((lambda *s: torch.randn(*s, dtype=torch.bfloat16) * 0.05)(Dff, D)),
        }
    _B_in = _B_setup()

    return {
        "A_x": _A_in["x"],
        "A_Lambda_re": _A_in["Lambda_re"],
        "A_Lambda_im": _A_in["Lambda_im"],
        "A_B_re": _A_in["B_re"],
        "A_B_im": _A_in["B_im"],
        "A_C_re": _A_in["C_re"],
        "A_C_im": _A_in["C_im"],
        "A_log_dt": _A_in["log_dt"],
        "A_Dskip": _A_in["Dskip"],
        "B_x": _B_in["x"],
        "B_w1": _B_in["w1"],
        "B_w2": _B_in["w2"],
        "gate_w": _w((lambda *s: torch.randn(*s, dtype=torch.bfloat16) * 0.05)(1024) * 16.0),
    }

def reference(A_x, A_Lambda_re, A_Lambda_im, A_B_re, A_B_im, A_C_re, A_C_im, A_log_dt, A_Dskip, B_x, B_w1, B_w2, gate_w):
    def _A_ref(x, Lambda_re, Lambda_im, B_re, B_im, C_re, C_im, log_dt, Dskip):
        Bsz, L, H = x.shape
        Lam = Lambda_re + 1j * Lambda_im
        Bmat = B_re + 1j * B_im
        Cmat = C_re + 1j * C_im
        dt = torch.exp(log_dt)
        Lam_bar = torch.exp(dt * Lam)
        B_bar = ((Lam_bar - 1.0) / Lam)[:, None] * Bmat
        Bu = torch.einsum("bld,pd->blp", x + 0j, B_bar)
        h = torch.zeros_like(Bu[:, 0, :])
        hs = []
        for t in range(L):
            h = Lam_bar[None, :] * h + Bu[:, t, :]
            hs.append(h)
        hseq = torch.stack(hs, 1)
        y = 2.0 * torch.einsum("blp,dp->bld", hseq, Cmat).real + x * Dskip[None, None, :]
        return y

    def _B_ref(x, w1, w2):
        h = torch.einsum("bsd,df->bsf", x, w1)
        zero = torch.zeros_like(h)
        h = torch.maximum(h, zero)
        return torch.einsum("bsf,fd->bsd", h, w2)

    x = A_x
    g = _sigmoid((x * gate_w).sum(-1, keepdims=True))
    a = _A_ref(x, A_Lambda_re, A_Lambda_im, A_B_re, A_B_im, A_C_re, A_C_im, A_log_dt, A_Dskip)
    b = _B_ref(x, B_w1, B_w2)
    return g * a + (1 - g) * b
```

```cpp
#include <cuda_runtime.h>
#include <cuda.h>
#include <cuda_bf16.h>
#include <stdint.h>

template <int TA, int TB>
__device__ __forceinline__ void wgmma_m64n256k16(float (&d)[128], uint32_t da, uint32_t db, int scale_d) {
  asm volatile("{\n.reg .pred p;\n.reg .b64 da, db;\nsetp.ne.b32 p, %130, 0;\n"
    "mov.b64 da, {%128, 0x40000040};\nmov.b64 db, {%129, 0x40000040};\n"
    "wgmma.mma_async.sync.aligned.m64n256k16.f32.bf16.bf16 "
    "{%0, %1, %2, %3, %4, %5, %6, %7, %8, %9, %10, %11, %12, %13, %14, %15, %16, %17, %18, %19, %20, %21, %22, %23, %24, %25, %26, %27, %28, %29, %30, %31, %32, %33, %34, %35, %36, %37, %38, %39, %40, %41, %42, %43, %44, %45, %46, %47, %48, %49, %50, %51, %52, %53, %54, %55, %56, %57, %58, %59, %60, %61, %62, %63, %64, %65, %66, %67, %68, %69, %70, %71, %72, %73, %74, %75, %76, %77, %78, %79, %80, %81, %82, %83, %84, %85, %86, %87, %88, %89, %90, %91, %92, %93, %94, %95, %96, %97, %98, %99, %100, %101, %102, %103, %104, %105, %106, %107, %108, %109, %110, %111, %112, %113, %114, %115, %116, %117, %118, %119, %120, %121, %122, %123, %124, %125, %126, %127}, da, db, p, 1, 1, %131, %132;\n}\n"
    : "+f"(d[0]), "+f"(d[1]), "+f"(d[2]), "+f"(d[3]), "+f"(d[4]), "+f"(d[5]), "+f"(d[6]), "+f"(d[7]), "+f"(d[8]), "+f"(d[9]), "+f"(d[10]), "+f"(d[11]), "+f"(d[12]), "+f"(d[13]), "+f"(d[14]), "+f"(d[15]), "+f"(d[16]), "+f"(d[17]), "+f"(d[18]), "+f"(d[19]), "+f"(d[20]), "+f"(d[21]), "+f"(d[22]), "+f"(d[23]), "+f"(d[24]), "+f"(d[25]), "+f"(d[26]), "+f"(d[27]), "+f"(d[28]), "+f"(d[29]), "+f"(d[30]), "+f"(d[31]), "+f"(d[32]), "+f"(d[33]), "+f"(d[34]), "+f"(d[35]), "+f"(d[36]), "+f"(d[37]), "+f"(d[38]), "+f"(d[39]), "+f"(d[40]), "+f"(d[41]), "+f"(d[42]), "+f"(d[43]), "+f"(d[44]), "+f"(d[45]), "+f"(d[46]), "+f"(d[47]), "+f"(d[48]), "+f"(d[49]), "+f"(d[50]), "+f"(d[51]), "+f"(d[52]), "+f"(d[53]), "+f"(d[54]), "+f"(d[55]), "+f"(d[56]), "+f"(d[57]), "+f"(d[58]), "+f"(d[59]), "+f"(d[60]), "+f"(d[61]), "+f"(d[62]), "+f"(d[63]), "+f"(d[64]), "+f"(d[65]), "+f"(d[66]), "+f"(d[67]), "+f"(d[68]), "+f"(d[69]), "+f"(d[70]), "+f"(d[71]), "+f"(d[72]), "+f"(d[73]), "+f"(d[74]), "+f"(d[75]), "+f"(d[76]), "+f"(d[77]), "+f"(d[78]), "+f"(d[79]), "+f"(d[80]), "+f"(d[81]), "+f"(d[82]), "+f"(d[83]), "+f"(d[84]), "+f"(d[85]), "+f"(d[86]), "+f"(d[87]), "+f"(d[88]), "+f"(d[89]), "+f"(d[90]), "+f"(d[91]), "+f"(d[92]), "+f"(d[93]), "+f"(d[94]), "+f"(d[95]), "+f"(d[96]), "+f"(d[97]), "+f"(d[98]), "+f"(d[99]), "+f"(d[100]), "+f"(d[101]), "+f"(d[102]), "+f"(d[103]), "+f"(d[104]), "+f"(d[105]), "+f"(d[106]), "+f"(d[107]), "+f"(d[108]), "+f"(d[109]), "+f"(d[110]), "+f"(d[111]), "+f"(d[112]), "+f"(d[113]), "+f"(d[114]), "+f"(d[115]), "+f"(d[116]), "+f"(d[117]), "+f"(d[118]), "+f"(d[119]), "+f"(d[120]), "+f"(d[121]), "+f"(d[122]), "+f"(d[123]), "+f"(d[124]), "+f"(d[125]), "+f"(d[126]), "+f"(d[127])
    : "r"(da), "r"(db), "r"(scale_d), "n"(TA), "n"(TB));
}

template <int TA, int TB>
__device__ __forceinline__ void wgmma_m64n224k16(float (&d)[112], uint32_t da, uint32_t db, int scale_d) {
  asm volatile("{\n.reg .pred p;\n.reg .b64 da, db;\nsetp.ne.b32 p, %114, 0;\n"
    "mov.b64 da, {%112, 0x40000040};\nmov.b64 db, {%113, 0x80000020};\n"
    "wgmma.mma_async.sync.aligned.m64n224k16.f32.bf16.bf16 "
    "{%0, %1, %2, %3, %4, %5, %6, %7, %8, %9, %10, %11, %12, %13, %14, %15, %16, %17, %18, %19, %20, %21, %22, %23, %24, %25, %26, %27, %28, %29, %30, %31, %32, %33, %34, %35, %36, %37, %38, %39, %40, %41, %42, %43, %44, %45, %46, %47, %48, %49, %50, %51, %52, %53, %54, %55, %56, %57, %58, %59, %60, %61, %62, %63, %64, %65, %66, %67, %68, %69, %70, %71, %72, %73, %74, %75, %76, %77, %78, %79, %80, %81, %82, %83, %84, %85, %86, %87, %88, %89, %90, %91, %92, %93, %94, %95, %96, %97, %98, %99, %100, %101, %102, %103, %104, %105, %106, %107, %108, %109, %110, %111}, da, db, p, 1, 1, %115, %116;\n}\n"
    : "+f"(d[0]), "+f"(d[1]), "+f"(d[2]), "+f"(d[3]), "+f"(d[4]), "+f"(d[5]), "+f"(d[6]), "+f"(d[7]), "+f"(d[8]), "+f"(d[9]), "+f"(d[10]), "+f"(d[11]), "+f"(d[12]), "+f"(d[13]), "+f"(d[14]), "+f"(d[15]), "+f"(d[16]), "+f"(d[17]), "+f"(d[18]), "+f"(d[19]), "+f"(d[20]), "+f"(d[21]), "+f"(d[22]), "+f"(d[23]), "+f"(d[24]), "+f"(d[25]), "+f"(d[26]), "+f"(d[27]), "+f"(d[28]), "+f"(d[29]), "+f"(d[30]), "+f"(d[31]), "+f"(d[32]), "+f"(d[33]), "+f"(d[34]), "+f"(d[35]), "+f"(d[36]), "+f"(d[37]), "+f"(d[38]), "+f"(d[39]), "+f"(d[40]), "+f"(d[41]), "+f"(d[42]), "+f"(d[43]), "+f"(d[44]), "+f"(d[45]), "+f"(d[46]), "+f"(d[47]), "+f"(d[48]), "+f"(d[49]), "+f"(d[50]), "+f"(d[51]), "+f"(d[52]), "+f"(d[53]), "+f"(d[54]), "+f"(d[55]), "+f"(d[56]), "+f"(d[57]), "+f"(d[58]), "+f"(d[59]), "+f"(d[60]), "+f"(d[61]), "+f"(d[62]), "+f"(d[63]), "+f"(d[64]), "+f"(d[65]), "+f"(d[66]), "+f"(d[67]), "+f"(d[68]), "+f"(d[69]), "+f"(d[70]), "+f"(d[71]), "+f"(d[72]), "+f"(d[73]), "+f"(d[74]), "+f"(d[75]), "+f"(d[76]), "+f"(d[77]), "+f"(d[78]), "+f"(d[79]), "+f"(d[80]), "+f"(d[81]), "+f"(d[82]), "+f"(d[83]), "+f"(d[84]), "+f"(d[85]), "+f"(d[86]), "+f"(d[87]), "+f"(d[88]), "+f"(d[89]), "+f"(d[90]), "+f"(d[91]), "+f"(d[92]), "+f"(d[93]), "+f"(d[94]), "+f"(d[95]), "+f"(d[96]), "+f"(d[97]), "+f"(d[98]), "+f"(d[99]), "+f"(d[100]), "+f"(d[101]), "+f"(d[102]), "+f"(d[103]), "+f"(d[104]), "+f"(d[105]), "+f"(d[106]), "+f"(d[107]), "+f"(d[108]), "+f"(d[109]), "+f"(d[110]), "+f"(d[111])
    : "r"(da), "r"(db), "r"(scale_d), "n"(TA), "n"(TB));
}

template <int TA, int TB>
__device__ __forceinline__ void wgmma_m64n192k16(float (&d)[96], uint32_t da, uint32_t db, int scale_d) {
  asm volatile("{\n.reg .pred p;\n.reg .b64 da, db;\nsetp.ne.b32 p, %98, 0;\n"
    "mov.b64 da, {%96, 0x40000040};\nmov.b64 db, {%97, 0x40000040};\n"
    "wgmma.mma_async.sync.aligned.m64n192k16.f32.bf16.bf16 "
    "{%0, %1, %2, %3, %4, %5, %6, %7, %8, %9, %10, %11, %12, %13, %14, %15, %16, %17, %18, %19, %20, %21, %22, %23, %24, %25, %26, %27, %28, %29, %30, %31, %32, %33, %34, %35, %36, %37, %38, %39, %40, %41, %42, %43, %44, %45, %46, %47, %48, %49, %50, %51, %52, %53, %54, %55, %56, %57, %58, %59, %60, %61, %62, %63, %64, %65, %66, %67, %68, %69, %70, %71, %72, %73, %74, %75, %76, %77, %78, %79, %80, %81, %82, %83, %84, %85, %86, %87, %88, %89, %90, %91, %92, %93, %94, %95}, da, db, p, 1, 1, %99, %100;\n}\n"
    : "+f"(d[0]), "+f"(d[1]), "+f"(d[2]), "+f"(d[3]), "+f"(d[4]), "+f"(d[5]), "+f"(d[6]), "+f"(d[7]), "+f"(d[8]), "+f"(d[9]), "+f"(d[10]), "+f"(d[11]), "+f"(d[12]), "+f"(d[13]), "+f"(d[14]), "+f"(d[15]), "+f"(d[16]), "+f"(d[17]), "+f"(d[18]), "+f"(d[19]), "+f"(d[20]), "+f"(d[21]), "+f"(d[22]), "+f"(d[23]), "+f"(d[24]), "+f"(d[25]), "+f"(d[26]), "+f"(d[27]), "+f"(d[28]), "+f"(d[29]), "+f"(d[30]), "+f"(d[31]), "+f"(d[32]), "+f"(d[33]), "+f"(d[34]), "+f"(d[35]), "+f"(d[36]), "+f"(d[37]), "+f"(d[38]), "+f"(d[39]), "+f"(d[40]), "+f"(d[41]), "+f"(d[42]), "+f"(d[43]), "+f"(d[44]), "+f"(d[45]), "+f"(d[46]), "+f"(d[47]), "+f"(d[48]), "+f"(d[49]), "+f"(d[50]), "+f"(d[51]), "+f"(d[52]), "+f"(d[53]), "+f"(d[54]), "+f"(d[55]), "+f"(d[56]), "+f"(d[57]), "+f"(d[58]), "+f"(d[59]), "+f"(d[60]), "+f"(d[61]), "+f"(d[62]), "+f"(d[63]), "+f"(d[64]), "+f"(d[65]), "+f"(d[66]), "+f"(d[67]), "+f"(d[68]), "+f"(d[69]), "+f"(d[70]), "+f"(d[71]), "+f"(d[72]), "+f"(d[73]), "+f"(d[74]), "+f"(d[75]), "+f"(d[76]), "+f"(d[77]), "+f"(d[78]), "+f"(d[79]), "+f"(d[80]), "+f"(d[81]), "+f"(d[82]), "+f"(d[83]), "+f"(d[84]), "+f"(d[85]), "+f"(d[86]), "+f"(d[87]), "+f"(d[88]), "+f"(d[89]), "+f"(d[90]), "+f"(d[91]), "+f"(d[92]), "+f"(d[93]), "+f"(d[94]), "+f"(d[95])
    : "r"(da), "r"(db), "r"(scale_d), "n"(TA), "n"(TB));
}

template <int TA, int TB>
__device__ __forceinline__ void wgmma_m64n128k16(float (&d)[64], uint32_t da, uint32_t db, int scale_d) {
  asm volatile("{\n.reg .pred p;\n.reg .b64 da, db;\nsetp.ne.b32 p, %66, 0;\n"
    "mov.b64 da, {%64, 0x40000040};\nmov.b64 db, {%65, 0x40000040};\n"
    "wgmma.mma_async.sync.aligned.m64n128k16.f32.bf16.bf16 "
    "{%0, %1, %2, %3, %4, %5, %6, %7, %8, %9, %10, %11, %12, %13, %14, %15, %16, %17, %18, %19, %20, %21, %22, %23, %24, %25, %26, %27, %28, %29, %30, %31, %32, %33, %34, %35, %36, %37, %38, %39, %40, %41, %42, %43, %44, %45, %46, %47, %48, %49, %50, %51, %52, %53, %54, %55, %56, %57, %58, %59, %60, %61, %62, %63}, da, db, p, 1, 1, %67, %68;\n}\n"
    : "+f"(d[0]), "+f"(d[1]), "+f"(d[2]), "+f"(d[3]), "+f"(d[4]), "+f"(d[5]), "+f"(d[6]), "+f"(d[7]), "+f"(d[8]), "+f"(d[9]), "+f"(d[10]), "+f"(d[11]), "+f"(d[12]), "+f"(d[13]), "+f"(d[14]), "+f"(d[15]), "+f"(d[16]), "+f"(d[17]), "+f"(d[18]), "+f"(d[19]), "+f"(d[20]), "+f"(d[21]), "+f"(d[22]), "+f"(d[23]), "+f"(d[24]), "+f"(d[25]), "+f"(d[26]), "+f"(d[27]), "+f"(d[28]), "+f"(d[29]), "+f"(d[30]), "+f"(d[31]), "+f"(d[32]), "+f"(d[33]), "+f"(d[34]), "+f"(d[35]), "+f"(d[36]), "+f"(d[37]), "+f"(d[38]), "+f"(d[39]), "+f"(d[40]), "+f"(d[41]), "+f"(d[42]), "+f"(d[43]), "+f"(d[44]), "+f"(d[45]), "+f"(d[46]), "+f"(d[47]), "+f"(d[48]), "+f"(d[49]), "+f"(d[50]), "+f"(d[51]), "+f"(d[52]), "+f"(d[53]), "+f"(d[54]), "+f"(d[55]), "+f"(d[56]), "+f"(d[57]), "+f"(d[58]), "+f"(d[59]), "+f"(d[60]), "+f"(d[61]), "+f"(d[62]), "+f"(d[63])
    : "r"(da), "r"(db), "r"(scale_d), "n"(TA), "n"(TB));
}

namespace {

constexpr int SEQ = 2048, DM = 1024, PS = 1024, FF = 3584;
constexpr int SLOT = 16384, RING = 12 * SLOT;
constexpr int SMEM_BYTES = 232448;
#define USEH 1
constexpr int KL = 12;
constexpr int SOLO = 6;
constexpr int XTRA = 4;
constexpr int LDAT = 4;
constexpr int W1D = 4;
constexpr int P1OFF = 4;
constexpr int LBK = 7;
constexpr int LBW = 2;
constexpr int STG = 8;
constexpr int KW = (32 - KL) / 2;
constexpr int S3 = 76 + KW;
static_assert(KL % 4 == 0 && KW > 8 && S3 - 4 + (2 * (XTRA - 1) + 1) / 3 >= 84, "x tile must be consumed before it is overwritten");
constexpr unsigned SPIN_LIMIT = 1u << 22;

struct Params {
  const __nv_bfloat16 *lam_re, *lam_im, *log_dt, *dskip, *gate_w;
  float* out;
  unsigned char tile[72];
  CUtensorMap xp, x, bre, bim, w1a, w1b, w1c, hs, hf, cre, cim, w2;
};

__device__ __align__(1024) __nv_bfloat16 g_Hs[2 * PS * SEQ];
__device__ __align__(1024) __nv_bfloat16 g_Hf[SEQ * FF];
__device__ unsigned long long g_agg[16 * PS];
__device__ unsigned long long g_gate[SEQ];
__device__ __align__(16) uint4 g_xch[128 * 8 * 256];
__device__ unsigned g_ready[5 * 16 * 32];
__device__ unsigned g_epoch[132];

__device__ __forceinline__ void die() { asm volatile("st.global.u32 [%0], %1;" ::"l"(0ull), "r"(0) : "memory"); }
__device__ __forceinline__ uint32_t smem_u32(const void* p) { return (uint32_t)__cvta_generic_to_shared(p); }
__device__ __forceinline__ void mbar_init(uint32_t bar, int cnt) {
  asm volatile("mbarrier.init.shared::cta.b64 [%0], %1;" ::"r"(bar), "r"(cnt));
}
__device__ __forceinline__ void mbar_wait(uint32_t bar, uint32_t parity) {
  asm volatile("{\n.reg .pred p;\n.reg .u32 n;\n.reg .u64 z;\nmov.u32 n, 0;\n"
               "LW:\nmbarrier.try_wait.parity.shared::cta.b64 p, [%0], %1;\n@p bra LD;\n"
               "add.u32 n, n, 1;\nsetp.lt.u32 p, n, %2;\n@p bra LW;\n"
               "mov.u64 z, 0;\nst.global.u32 [z], n;\nLD:\n}\n" ::"r"(bar), "r"(parity), "n"(SPIN_LIMIT) : "memory");
}
#define ELECT "{\n.reg .pred e;\nelect.sync _|e, 0xffffffff;\n@e "
#define TMA_LD(dim) "cp.async.bulk.tensor." dim ".shared::cluster.global.mbarrier::complete_tx::bytes"
__device__ __forceinline__ void expect_tx(uint32_t bar, uint32_t bytes) {
  asm volatile(ELECT "mbarrier.arrive.expect_tx.shared::cta.b64 _, [%0], %1;\n}\n" ::"r"(bar), "r"(bytes) : "memory");
}
__device__ __forceinline__ void tma2(uint32_t dst, const CUtensorMap* tm, uint32_t bar, int c0, int c1) {
  asm volatile(ELECT TMA_LD("2d") " [%0], [%1, {%3, %4}], [%2];\n}\n" ::"r"(dst), "l"(tm), "r"(bar), "r"(c0), "r"(c1) : "memory");
}
__device__ __forceinline__ void tma3(uint32_t dst, const CUtensorMap* tm, uint32_t bar, int c1, int c2) {
  asm volatile(ELECT TMA_LD("3d") " [%0], [%1, {%5, %3, %4}], [%2];\n}\n" ::"r"(dst), "l"(tm), "r"(bar), "r"(c1), "r"(c2), "r"(0) : "memory");
}
__device__ __forceinline__ void tma4(uint32_t dst, const CUtensorMap* tm, uint32_t bar, int c0, int c2) {
  asm volatile(ELECT TMA_LD("4d") " [%0], [%1, {%3, %5, %4, %5}], [%2];\n}\n" ::"r"(dst), "l"(tm), "r"(bar), "r"(c0), "r"(c2), "r"(0) : "memory");
}
__device__ __forceinline__ void tma2_mc(uint32_t dst, const CUtensorMap* tm, uint32_t bar, int c0, int c1) {
  asm volatile(ELECT TMA_LD("2d") ".multicast::cluster [%0], [%1, {%3, %4}], [%2], %5;\n}\n"
               ::"r"(dst), "l"(tm), "r"(bar), "r"(c0), "r"(c1), "h"((uint16_t)3) : "memory");
}
__device__ __forceinline__ void tma3_mc(uint32_t dst, const CUtensorMap* tm, uint32_t bar, int c0, int c1) {
  asm volatile(ELECT TMA_LD("3d") ".multicast::cluster [%0], [%1, {%3, %4, %5}], [%2], %6;\n}\n"
               ::"r"(dst), "l"(tm), "r"(bar), "r"(c0), "r"(c1), "r"(0), "h"((uint16_t)3) : "memory");
}
__device__ __forceinline__ void tma5_mc(uint32_t dst, const CUtensorMap* tm, uint32_t bar, int c0, int c4) {
  asm volatile(ELECT TMA_LD("5d") ".multicast::cluster [%0], [%1, {%3, %5, %5, %5, %4}], [%2], %6;\n}\n"
               ::"r"(dst), "l"(tm), "r"(bar), "r"(c0), "r"(c4), "r"(0), "h"((uint16_t)3) : "memory");
}
__device__ __forceinline__ void pf_map(const CUtensorMap* tm) { asm volatile(ELECT "prefetch.tensormap [%0];\n}\n" ::"l"(tm) : "memory"); }
__device__ __forceinline__ void wg_fence() { asm volatile("wgmma.fence.sync.aligned;" ::: "memory"); }
__device__ __forceinline__ void wg_commit() { asm volatile("wgmma.commit_group.sync.aligned;" ::: "memory"); }
template <int N> __device__ __forceinline__ void wg_wait() { asm volatile("wgmma.wait_group.sync.aligned %0;" ::"n"(N) : "memory"); }
template <int N> __device__ __forceinline__ void fence_acc(float (&a)[N]) {
#pragma unroll
  for (int i = 0; i < N; i++) asm volatile("" : "+f"(a[i])::"memory");
}
__device__ __forceinline__ void wgmma_up(float (&d)[128], uint32_t da, uint32_t db, int sc) { wgmma_m64n256k16<0, 1>(d, da, db, sc); }
__device__ __forceinline__ void wgmma_up(float (&d)[112], uint32_t da, uint32_t db, int sc) { wgmma_m64n224k16<0, 1>(d, da, db, sc); }
template <uint32_t LBO> __device__ __forceinline__ uint32_t mk_desc2(uint32_t addr16) { return addr16 + ((LBO >> 4) << 16); }
__device__ __forceinline__ int fresh_tid() { int t; asm volatile("mov.u32 %0, %%tid.x;" : "=r"(t)); return t; }
template <class T> __device__ __forceinline__ T* pin(T* ptr) { asm volatile("" : "+l"(ptr)); return ptr; }
__device__ __forceinline__ void bar_arrive(int id, int cnt) { asm volatile("bar.arrive %0, %1;" ::"r"(id), "r"(cnt) : "memory"); }
__device__ __forceinline__ void bar_sync(int id, int cnt) { asm volatile("bar.sync %0, %1;" ::"r"(id), "r"(cnt) : "memory"); }
__device__ __forceinline__ uint32_t pack_bf16(float lo, float hi) {
  uint32_t r; asm("cvt.rn.bf16x2.f32 %0, %1, %2;" : "=r"(r) : "f"(hi), "f"(lo)); return r;
}
__device__ __forceinline__ uint32_t pack_bf16_relu(float lo, float hi) {
  uint32_t r; asm("cvt.rn.relu.bf16x2.f32 %0, %1, %2;" : "=r"(r) : "f"(hi), "f"(lo)); return r;
}
__device__ __forceinline__ float bf_lo(uint32_t v) { return __uint_as_float(v << 16); }
__device__ __forceinline__ float bf_hi(uint32_t v) { return __uint_as_float(v & 0xFFFF0000u); }
__device__ __forceinline__ uint32_t mul_bf16x2(uint32_t a, uint32_t b) {
  uint32_t r; asm volatile("mul.rn.bf16x2 %0, %1, %2;" : "=r"(r) : "r"(a), "r"(b)); return r;
}
__device__ __forceinline__ void stg128(void* p, uint32_t a, uint32_t b, uint32_t c, uint32_t d) {
  asm volatile("st.global.v4.u32 [%0], {%1,%2,%3,%4};" ::"l"(p), "r"(a), "r"(b), "r"(c), "r"(d) : "memory");
}
__device__ __forceinline__ float bfround(float v) { return __bfloat162float(__float2bfloat16_rn(v)); }
__device__ __forceinline__ int swap_rows(int r) { return (r & 7) | ((r & 24) << 2) | ((r & 96) >> 2); }

struct cpx { float r, i; };
__device__ __forceinline__ cpx cmul(cpx a, cpx b) { return {a.r * b.r - a.i * b.i, a.r * b.i + a.i * b.r}; }
__device__ __forceinline__ cpx cfma(cpx a, cpx b, cpx c) {
  return {fmaf(a.r, b.r, fmaf(-a.i, b.i, c.r)), fmaf(a.r, b.i, fmaf(a.i, b.r, c.i))};
}
__device__ __forceinline__ cpx csq(cpx a) { return {a.r * a.r - a.i * a.i, 2.f * a.r * a.i}; }
__device__ __forceinline__ cpx cshfl_up4(cpx a, int d) {
  return {__shfl_up_sync(0xffffffffu, a.r, d, 4), __shfl_up_sync(0xffffffffu, a.i, d, 4)};
}
__device__ __forceinline__ cpx cpow_q(cpx b, cpx b2, int q) {
  cpx p = (q & 1) ? b : cpx{1.f, 0.f};
  cpx t = cmul(p, b2);
  return (q & 2) ? t : p;
}

template <bool H>
__global__ void __cluster_dims__(2, 1, 1) __launch_bounds__(384, 1)
fused_kernel(const __grid_constant__ Params p) {
  extern __shared__ __align__(1024) uint8_t smem_raw[];
  const uint32_t sbase = smem_u32(smem_raw);
  const uint32_t sx = sbase + RING;
  const uint32_t full0 = sx + 2 * SLOT, empty0 = full0 + 64, rdy0 = full0 + 128, gdone = full0 + 200, sgate = full0 + 240, stab = full0 + 1024;
  const int tid = threadIdx.x, warp = __shfl_sync(0xffffffffu, tid >> 5, 0), wg = warp >> 2, lane = tid & 31;
  constexpr int NA = H ? 224 : 256;
  constexpr int BA = NA / 16;
  constexpr int SF = 48 + BA + 12;
  constexpr int NC = H ? 2 : 0;
  const int rank = blockIdx.x & 1, item = p.tile[blockIdx.x >> 1];
  const bool helper = H && item >= 64;
  const int j = item & 7, mw = (item >> 3) * 2 + rank, mh = (item & 1) * 2 + rank;
  const int m = helper ? mh : mw;
  const int col1 = helper ? 8 * (NA + 192) : NA * j;
  const CUtensorMap* map1 = H && !helper ? &p.w1c : &p.w1b;
  const uint32_t bytes1 = SLOT + (H && !helper ? 224 : 256) * 128;

  if (tid == 0) {
    if (sbase & 1023) die();
    for (int i = 0; i < 8; i++) { mbar_init(full0 + 8 * i, 1); mbar_init(empty0 + 8 * i, 4); }
    for (int i = 0; i < 13; i++) mbar_init(rdy0 + 8 * i, 1);
    asm volatile("fence.mbarrier_init.release.cluster;" ::: "memory");
  }
  __syncwarp();
  asm volatile("barrier.cluster.arrive.relaxed.aligned;" ::: "memory");
  if (warp == 0) {
    expect_tx(full0, bytes1);
    tma2(sbase, &p.x, full0, 0, 128 * m);
  } else if (warp == 1) {
    pf_map(&p.x);
    pf_map(map1);
  }
  asm volatile("barrier.cluster.wait.aligned;" ::: "memory");
  if (warp == 0) tma3_mc(sbase + (1 + rank) * SLOT, map1, full0, col1, 32 * rank);
#define STORE_CASE(b, arr, half) case b: { const uint32_t og = (b) < (half) ? og0 : og1; \
            stg128(hfp + ((b) < (half) ? 32 * (b) : 32 * FF + 32 * ((b) - (half))), mul_bf16x2(arr[4 * (b)], og), mul_bf16x2(arr[4 * (b) + 1], og), \
                   mul_bf16x2(arr[4 * (b) + 2], og), mul_bf16x2(arr[4 * (b) + 3], og)); } break;
  if (__builtin_expect(H && helper && wg != 0, 0)) {
    asm volatile("setmaxnreg.inc.sync.aligned.u32 232;");
    const int w = wg - 1, m = mh;
    constexpr uint32_t S16 = SLOT / 16;
    uint32_t s = 0, rel0, pk[64], og0 = 0, og1 = 0;
    asm volatile("mapa.shared::cluster.u32 %0, %1, %2;" : "=r"(rel0) : "r"(empty0), "r"(tid & 1));
    auto wait_full = [&]() { mbar_wait(full0 + 8 * (s & 7), (s >> 3) & 1); };
    auto release = [&](uint32_t ss) {
      if ((tid & 127) < 2) asm volatile("mbarrier.arrive.shared::cluster.b64 _, [%0];" ::"r"(rel0 + 8 * (ss & 7)) : "memory");
    };
    auto stage3 = [&]() { return ((sbase & 0x3FFFF) >> 4) + (s & 3) * (3 * S16); };
    auto lds_f = [&](int t, uint32_t base) { unsigned short v; asm volatile("ld.shared.u16 %0, [%1];" : "=h"(v) : "r"(base + 2 * t + 16 * (t >> 5)) : "memory"); return bf_lo(v); };
      float acc[128];
      __nv_bfloat16* hfp = nullptr;
#pragma unroll 1
      for (int r = 0; r < 5; r++) {
#pragma unroll 1
        for (int k = 0; k < 16; k++) {
          if (r < 4) {
            wait_full();
            const uint32_t a = stage3();
            const uint32_t da = mk_desc2<16>(a + w * 512), db = mk_desc2<4096>(a + S16);
            wg_fence();
            wgmma_m64n256k16<0, 1>(acc, da + 0, db, k != 0);
            wgmma_m64n256k16<0, 1>(acc, da + 2, db + 128, 1);
            wgmma_m64n256k16<0, 1>(acc, da + 4, db + S16, 1);
            wgmma_m64n256k16<0, 1>(acc, da + 6, db + S16 + 128, 1);
            wg_commit();
            wg_wait<1>();
            if (k > 0) release(s - 1);
            s++;
          }
          if (r > 0) {
            switch (k) {
              STORE_CASE(0, pk, 8) STORE_CASE(1, pk, 8) STORE_CASE(2, pk, 8) STORE_CASE(3, pk, 8)
              STORE_CASE(4, pk, 8) STORE_CASE(5, pk, 8) STORE_CASE(6, pk, 8) STORE_CASE(7, pk, 8)
              STORE_CASE(8, pk, 8) STORE_CASE(9, pk, 8) STORE_CASE(10, pk, 8) STORE_CASE(11, pk, 8)
              STORE_CASE(12, pk, 8) STORE_CASE(13, pk, 8) STORE_CASE(14, pk, 8)
              default: STORE_CASE(15, pk, 8)
            }
          }
        }
        if (r > 0) bar_arrive(1, 288);
        wg_wait<0>();
        fence_acc(acc);
        if (r < 4) {
          release(s - 1);
          mbar_wait(rdy0 + 24, 0);
          const int t2 = fresh_tid(), q = t2 & 3, row0 = 64 * w + ((t2 & 127) >> 5) * 16 + ((t2 & 31) >> 2), r0 = swap_rows(row0);
          const float g0 = lds_f(row0, sx + 320 * r), g1 = lds_f(row0 + 8, sx + 320 * r);
          og0 = pack_bf16(1.f - g0, 1.f - g0);
          og1 = pack_bf16(1.f - g1, 1.f - g1);
          hfp = pin(g_Hf + (size_t)(128 * (m + 4 * r) + r0) * FF + 8 * q + 8 * (NA + 192));
        }
#pragma unroll
        for (int i = 0; i < 32; i++) {
          pk[i] = pack_bf16_relu(acc[4 * i], acc[4 * i + 1]);
          pk[32 + i] = pack_bf16_relu(acc[4 * i + 2], acc[4 * i + 3]);
        }
      }
    asm volatile("barrier.cluster.arrive.relaxed.aligned;\nbarrier.cluster.wait.aligned;" ::: "memory");
  } else if (wg != 0) {
    asm volatile("setmaxnreg.inc.sync.aligned.u32 232;");
    const int m = mw;
    const int w = wg - 1, jw = (tid >> 5) & 3, q = lane & 3, r8 = lane >> 2;
    const int row0 = 64 * w + 16 * jw + r8;
    uint32_t s = 0;
    const uint32_t dbase = (sbase & 0x3FFFF) >> 4;
    auto wait_full = [&]() { mbar_wait(full0 + 8 * (s & 7), (s >> 3) & 1); };
    uint32_t rel0;
    asm volatile("mapa.shared::cluster.u32 %0, %1, %2;" : "=r"(rel0) : "r"(empty0), "r"(tid & 1));
    const bool releaser = (tid & 127) < 2;
    auto release = [&](uint32_t ss) {
      if (releaser) asm volatile("mbarrier.arrive.shared::cluster.b64 _, [%0];" ::"r"(rel0 + 8 * (ss & 7)) : "memory");
    };
    auto stage3 = [&]() { return dbase + (s & 3) * (3 * SLOT / 16); };
    auto lds_f = [&](int t, uint32_t base) { unsigned short v; asm volatile("ld.shared.u16 %0, [%1];" : "=h"(v) : "r"(base + 2 * t + 16 * (t >> 5)) : "memory"); return bf_lo(v); };
    constexpr uint32_t S16 = SLOT / 16;
    auto hold = [&](bool last) { if (last && w == 1) bar_sync(4, 256); };
    auto drain = [&]() { if (w == 0) { wg_wait<1>(); bar_arrive(4, 256); } wg_wait<0>(); };

    const int r0 = swap_rows(row0);
    uint32_t pk[64];
    uint32_t og0 = 0, og1 = 0;
    {
      float acc[NA / 2];
#pragma unroll 1
      for (int k = 0; k < 16; k++) {
        wait_full();
        const uint32_t a = stage3();
        constexpr uint32_t K16 = H ? 64 : 128;
        const uint32_t da = mk_desc2<16>(a + w * 512), db = mk_desc2<32 * K16>(a + S16);
        hold(k == 15);
        wg_fence();
        wgmma_up(acc, da + 0, db, k != 0);
        wgmma_up(acc, da + 2, db + K16, 1);
        wgmma_up(acc, da + 4, db + S16, 1);
        wg_commit();
        wgmma_up(acc, da + 6, db + S16 + K16, 1);
        wg_commit();
        wg_wait<2>();
        if (k > 0) release(s - 1);
        s++;
      }
      drain();
      fence_acc(acc);
      release(s - 1);
#pragma unroll
      for (int i = 0; i < NA / 8; i++) {
        pk[i] = pack_bf16_relu(acc[4 * i], acc[4 * i + 1]);
        pk[NA / 8 + i] = pack_bf16_relu(acc[4 * i + 2], acc[4 * i + 3]);
      }
    }

    uint32_t pa[48];
    {
      float acc[96];
      __nv_bfloat16* hfp = nullptr;
#pragma unroll 1
      for (int k = 0; k < 16; k++) {
        wait_full();
        const uint32_t a = stage3();
        const uint32_t ax = (k >> 1) == (j ^ 1) ? dbase + (12 + (k & 1)) * S16 : a;
        const uint32_t da = mk_desc2<16>(ax + w * 512), db = mk_desc2<4096>(a + S16);
        hold(k == 15);
        wg_fence();
        wgmma_m64n192k16<0, 1>(acc, da + 0, db, k != 0);
        wgmma_m64n192k16<0, 1>(acc, da + 2, db + 128, 1);
        wgmma_m64n192k16<0, 1>(acc, da + 4, db + S16, 1);
        wg_commit();
        wgmma_m64n192k16<0, 1>(acc, da + 6, db + S16 + 128, 1);
        wg_commit();
        wg_wait<2>();
        if (k > 0) release(s - 1);
        s++;
        constexpr int K0 = H ? 2 : 0;
        if (k == K0) {
          mbar_wait(rdy0 + 24, 0);
          const float g0 = lds_f(row0, sgate), g1 = lds_f(row0 + 8, sgate);
          og0 = pack_bf16(1.f - g0, 1.f - g0);
          og1 = pack_bf16(1.f - g1, 1.f - g1);
          hfp = pin(g_Hf + (size_t)(128 * m + r0) * FF + 8 * q + NA * j);
        }
        constexpr int HF = NA / 32;
        switch (k - K0) {
          STORE_CASE(0, pk, HF) STORE_CASE(1, pk, HF) STORE_CASE(2, pk, HF) STORE_CASE(3, pk, HF)
          STORE_CASE(4, pk, HF) STORE_CASE(5, pk, HF) STORE_CASE(6, pk, HF) STORE_CASE(7, pk, HF)
          STORE_CASE(8, pk, HF) STORE_CASE(9, pk, HF) STORE_CASE(10, pk, HF) STORE_CASE(11, pk, HF)
          STORE_CASE(12, pk, HF) STORE_CASE(13, pk, HF)
          default:
            if constexpr (!H) { switch (k) { STORE_CASE(14, pk, HF) default: STORE_CASE(15, pk, HF) } }
        }
      }
      bar_arrive(1, 288);
      drain();
      fence_acc(acc);
      release(s - 1);
#pragma unroll
      for (int i = 0; i < 24; i++) {
        pa[i] = pack_bf16_relu(acc[4 * i], acc[4 * i + 1]);
        pa[24 + i] = pack_bf16_relu(acc[4 * i + 2], acc[4 * i + 3]);
      }
    }

    cpx st[2];
    {
      float are[64], aim[64];
      __nv_bfloat16* hfp = nullptr;
#pragma unroll 1
      for (int k = 0; k < 16; k++) {
        wait_full();
        const uint32_t a = stage3();
        const uint32_t db = mk_desc2<16>(a), dr = mk_desc2<16>(a + S16 + w * 512), di = mk_desc2<16>(a + 2 * S16 + w * 512);
        hold(k == 15);
        wg_fence();
#pragma unroll
        for (int kk = 0; kk < 4; kk++) {
          if (kk == 3) { wg_commit(); }
          wgmma_m64n128k16<0, 0>(are, dr + 2 * kk, db + 2 * kk, (k | kk) != 0);
          wgmma_m64n128k16<0, 0>(aim, di + 2 * kk, db + 2 * kk, (k | kk) != 0);
        }
        wg_commit();
        wg_wait<2>();
        if (k > 0) release(s - 1);
        s++;
        if (k == 0) hfp = pin(g_Hf + (size_t)(128 * m + r0) * FF + 8 * q + 8 * NA + 192 * j);
        switch (k) {
          STORE_CASE(0, pa, 6) STORE_CASE(1, pa, 6) STORE_CASE(2, pa, 6) STORE_CASE(3, pa, 6)
          STORE_CASE(4, pa, 6) STORE_CASE(5, pa, 6) STORE_CASE(6, pa, 6) STORE_CASE(7, pa, 6)
          STORE_CASE(8, pa, 6) STORE_CASE(9, pa, 6) STORE_CASE(10, pa, 6) STORE_CASE(11, pa, 6)
          case 12: bar_arrive(2, 288); break;
          case 13: mbar_wait(rdy0 + 40, 0); break;
          default: break;
        }
      }
      drain();
      fence_acc(are); fence_acc(aim);
      release(s - 1);
#pragma unroll
      for (int i = 0; i < 16; i++) {
#pragma unroll
        for (int e = 0; e < 2; e++) {
          const int o = 16 * (i >> 2) + 2 * (i & 3) + e;
          pk[o] = pack_bf16(are[4 * i + e], aim[4 * i + e]);
          pk[o + 8] = pack_bf16(are[4 * i + 2 + e], aim[4 * i + 2 + e]);
        }
      }
    }

    {
      float acc[128];
      float (&accO)[64] = *reinterpret_cast<float(*)[64]>(&acc[0]);
      float (&accP)[64] = *reinterpret_cast<float(*)[64]>(&acc[64]);
      auto stepF = [&](int k) {
        wait_full();
        const uint32_t a = stage3();
        const uint32_t da = mk_desc2<16>(a + w * 512), db = mk_desc2<8192>(a + S16);
        wg_fence();
#pragma unroll
        for (int kk = 0; kk < 4; kk++) {
          wgmma_m64n256k16<0, 1>(acc, da + 2 * kk, db + 128 * kk, (k | kk) != 0);
        }
        wg_commit();
        wg_wait<1>();
        if (k > 0) release(s - 1);
        s++;
      };
      auto get_tag = [&]() { unsigned t; asm volatile("ld.shared.u32 %0, [%1];" : "=r"(t) : "r"(sgate + 576) : "memory"); return t; };
      {
      const int tid4 = fresh_tid(), q = tid4 & 3, row0 = 64 * w + ((tid4 & 127) >> 5) * 16 + ((tid4 & 31) >> 2);
      auto tab = [&](int row, int c) {
        cpx t;
        asm volatile("ld.shared.v2.f32 {%0, %1}, [%2];" : "=f"(t.r), "=f"(t.i) : "r"(stab + 16 * row0 + 128 * c + 8 * row) : "memory");
        return t;
      };
      auto frow = [&]() { const int t = fresh_tid(); return 64 * w + ((t & 127) >> 5) * 16 + ((t & 31) >> 2); };
      auto agg_ptr = [&]() { return &g_agg[(m - 1 - q) * PS + 128 * j + frow()]; };
      st[0] = st[1] = cpx{0.f, 0.f};
#define PASS1_CASE(b) case b: { const cpx l0 = tab(0, 0), l1 = tab(0, 1); \
            _Pragma("unroll") for (int t = 0; t < 8; t++) { \
              st[0] = cfma(l0, st[0], cpx{bf_lo(pk[16 * (b) + t]), bf_hi(pk[16 * (b) + t])}); \
              st[1] = cfma(l1, st[1], cpx{bf_lo(pk[16 * (b) + 8 + t]), bf_hi(pk[16 * (b) + 8 + t])}); } } break;
#pragma unroll 1
      for (int k = 0; k < LBK + STG * w; k++) {
        stepF(k);
        switch (k - P1OFF * w) {
          PASS1_CASE(0) PASS1_CASE(1) PASS1_CASE(2) PASS1_CASE(3)
          case 4: {
            const unsigned tag = get_tag();
#pragma unroll
            for (int c = 0; c < 2; c++) {
              const cpx l32 = csq(csq(csq(csq(csq(tab(0, c)))))), l64 = csq(l32);
              cpx v = cshfl_up4(st[c], 1);
              if (q >= 1) st[c] = cfma(l32, v, st[c]);
              v = cshfl_up4(st[c], 2);
              if (q >= 2) st[c] = cfma(l64, v, st[c]);
              if (q == 3) {
                const unsigned long long v8 = ((unsigned long long)__float_as_uint(st[c].i) << 32) | ((__float_as_uint(st[c].r) & ~3u) | tag);
                asm volatile("st.relaxed.gpu.global.u64 [%0], %1;" ::"l"(agg_ptr() + 4 * PS + 8 * c), "l"(v8) : "memory");
              }
              st[c] = cshfl_up4(st[c], 1);
              if (q == 0) st[c] = cpx{0.f, 0.f};
            }
          } break;
          default: break;
        }
      }
      {
        unsigned long long ag[8];
        auto load_agg = [&]() {
          const unsigned tag = get_tag();
          const unsigned long long* agp = agg_ptr();
#pragma unroll
          for (int u = 0; u < 8; u++) {
            ag[u] = tag;
            if (m - 1 - q - 4 * (u & 3) >= 0)
              asm volatile("ld.relaxed.gpu.global.u64 %0, [%1];" : "=l"(ag[u]) : "l"(agp - 4 * PS * (u & 3) + 8 * (u >> 2)) : "memory");
          }
        };
#pragma unroll 1
        for (unsigned n = 0;; n++) {
          load_agg();
#pragma unroll 1
          for (int k = n ? LBW : 0; k < LBW; k++) stepF(1);
          const unsigned tag = get_tag();
          bool ok = true;
#pragma unroll
          for (int u = 0; u < 8; u++) ok = ok && ((unsigned)ag[u] & 3u) == tag;
          if (__all_sync(0xffffffffu, ok)) break;
          if (n > SPIN_LIMIT) die();
        }
#pragma unroll
        for (int c = 0; c < 2; c++) {
          const cpx l32 = csq(csq(csq(csq(csq(tab(0, c)))))), l64 = csq(l32), l128 = csq(l64), l256 = csq(l128), l512 = csq(l256);
          cpx a[4];
#pragma unroll
          for (int u = 0; u < 4; u++)
            a[u] = cpx{__uint_as_float((unsigned)ag[4 * c + u] & ~3u), __uint_as_float((unsigned)(ag[4 * c + u] >> 32))};
          cpx cq = cfma(l512, cfma(l512, cfma(l512, a[3], a[2]), a[1]), a[0]);
          cq = cmul(cpow_q(l128, l256, q), cq);
          cq.r += __shfl_xor_sync(0xffffffffu, cq.r, 1); cq.i += __shfl_xor_sync(0xffffffffu, cq.i, 1);
          cq.r += __shfl_xor_sync(0xffffffffu, cq.r, 2); cq.i += __shfl_xor_sync(0xffffffffu, cq.i, 2);
          st[c] = cfma(cpow_q(l32, l64, q), cq, st[c]);
        }
      }
      {
        __nv_bfloat16* hs = pin(g_Hs + (size_t)(128 * j + row0) * SEQ + 128 * m + 8 * q);
#define UNPACK_CASE(b) case b: { _Pragma("unroll") for (int i = 0; i < 8; i++) { \
              asm volatile("shl.b32 %0, %1, 16;" : "=f"(ur[i]) : "r"(pk[8 * (b) + i])); \
              asm volatile("and.b32 %0, %1, 0xffff0000;" : "=f"(ui[i]) : "r"(pk[8 * (b) + i])); } } break;
#pragma unroll 1
        for (int k = 0; k < 8; k++) {
          const int blk = k >> 1, c = k & 1;
          stepF(1);
          float ur[8], ui[8];
          switch (k) {
            UNPACK_CASE(0) UNPACK_CASE(1) UNPACK_CASE(2) UNPACK_CASE(3) UNPACK_CASE(4) UNPACK_CASE(5) UNPACK_CASE(6)
            default: UNPACK_CASE(7)
          }
          const cpx la = tab(0, c), co = tab(1, c);
          uint32_t ore[4], oim[4];
#pragma unroll
          for (int t2 = 0; t2 < 4; t2++) {
            uint32_t gt;
            asm volatile("ld.shared.u32 %0, [%1];" : "=r"(gt) : "r"(sgate + 80 * q + 16 * blk + 4 * t2) : "memory");
            st[0] = cfma(la, st[0], cpx{ur[2 * t2], ui[2 * t2]});
            const float r0 = fmaf(co.r, st[0].r, -co.i * st[0].i), i0 = fmaf(-co.r, st[0].i, -co.i * st[0].r);
            st[0] = cfma(la, st[0], cpx{ur[2 * t2 + 1], ui[2 * t2 + 1]});
            const float r1 = fmaf(co.r, st[0].r, -co.i * st[0].i), i1 = fmaf(-co.r, st[0].i, -co.i * st[0].r);
            ore[t2] = mul_bf16x2(pack_bf16(r0, r1), gt);
            oim[t2] = mul_bf16x2(pack_bf16(i0, i1), gt);
          }
          __nv_bfloat16* dst = hs + (size_t)(8 * c) * SEQ + 32 * blk;
          stg128(dst, ore[0], ore[1], ore[2], ore[3]);
          stg128(dst + (size_t)PS * SEQ, oim[0], oim[1], oim[2], oim[3]);
          const cpx t = st[0]; st[0] = st[1]; st[1] = t;
        }
      }
      }
      if (w == 0) bar_arrive(3, 160); else bar_arrive(8, 160);
#pragma unroll 1
      for (int k = LBK + STG * w + LBW + 8; k < SF - 48; k++) stepF(1);
      const int tid = fresh_tid(), q = tid & 3, r8 = (tid & 31) >> 2, r0 = swap_rows(64 * w + 16 * ((tid >> 5) & 3) + r8);
      float sk[64];
#pragma unroll 1
      for (int k = 0; k < KW; k++) {
        wait_full();
        const uint32_t a = stage3();
        const uint32_t da = mk_desc2<16>(a + w * 512), db = mk_desc2<16>(a + S16);
        wg_fence();
#pragma unroll
        for (int kk = 0; kk < 4; kk++) wgmma_m64n256k16<1, 0>(acc, da + 128 * kk, db + 2 * kk, 1);
        wg_commit();
        wg_wait<1>();
        release(s - 1);
        s++;
#define SKIP_CASE(b) case 2 * (b): { \
            const float g0 = lds_f(r0, sgate), g1 = lds_f(r0 + 32, sgate); \
            _Pragma("unroll") for (int i = 4 * (b); i < 4 * (b) + 4; i++) { \
              uint32_t dk, xa, xb; \
              const uint32_t xad = sx + r0 * 128 + 4 * q + (i >> 3) * SLOT + (((i & 7) ^ r8) << 4); \
              asm volatile("ld.shared.u32 %0, [%1];" : "=r"(dk) : "r"(sgate + 320 + 4 * q + 16 * i) : "memory"); \
              asm volatile("ld.shared.u32 %0, [%1];" : "=r"(xa) : "r"(xad) : "memory"); \
              asm volatile("ld.shared.u32 %0, [%1];" : "=r"(xb) : "r"(xad + 32 * 128) : "memory"); \
              xa = mul_bf16x2(xa, dk); xb = mul_bf16x2(xb, dk); \
              sk[4 * i] = g0 * bf_lo(xa); sk[4 * i + 1] = g0 * bf_hi(xa); sk[4 * i + 2] = g1 * bf_lo(xb); sk[4 * i + 3] = g1 * bf_hi(xb); \
            } } break;
        switch (k - w) {
          SKIP_CASE(0) SKIP_CASE(1) SKIP_CASE(2) SKIP_CASE(3)
          default: break;
        }
      }
#pragma unroll 1
      for (int k = 0; k < NC; k++) stepF(1);
      uint32_t in[32];
      auto load_in = [&]() {
        const uint4* xi = g_xch + (size_t)(8 * m + j) * 2048 + (tid - 128);
#pragma unroll
        for (int i = 0; i < 8; i++)
          asm volatile("{\n.reg .b128 t;\n.reg .b64 a, b;\nld.relaxed.gpu.global.b128 t, [%4];\nmov.b128 {a, b}, t;\nmov.b64 {%0, %1}, a;\nmov.b64 {%2, %3}, b;\n}\n"
                       : "=r"(in[4 * i]), "=r"(in[4 * i + 1]), "=r"(in[4 * i + 2]), "=r"(in[4 * i + 3]) : "l"(xi + 256 * i) : "memory");
      };
      uint32_t a2 = dbase + ((S3 & 3) * 3 / 2) * (2 * S16);
      int nl = 0;
      auto step = [&](bool rel) {
        const bool xt = nl == KL - SOLO;
        if (xt) mbar_wait(rdy0 + 56, 0); else wait_full();
        const uint32_t a = xt ? dbase + 12 * S16 : a2;
        const uint32_t da = mk_desc2<16>(a + w * 512), db = mk_desc2<16>(a + S16);
        wg_fence();
#pragma unroll
        for (int kk = 0; kk < 4; kk++) wgmma_m64n128k16<1, 0>(accO, da + 128 * kk, db + 2 * kk, 1);
        wg_commit();
        if (rel) { wg_wait<1>(); release(s - 1); }
        nl++;
        if (!xt) {
          s++;
          a2 += 2 * S16;
          if (a2 == dbase + 12 * S16) a2 = dbase;
        }
      };
      uint4* xo = pin(g_xch + (size_t)(8 * m + (j ^ 1)) * 2048 + (tid - 128));
      const uint32_t par = get_tag() & 1u;
      auto send = [&](int u) {
        asm volatile("{\n.reg .b128 t;\n.reg .b64 a, b;\n.reg .b32 c0, c1, c2, c3;\n.reg .f32 f0, f1;\n"
                     "add.f32 f0, %2, %10;\nadd.f32 f1, %3, %11;\ncvt.rn.bf16x2.f32 c0, f1, f0;\nlop3.b32 c0, c0, 0xfffffffe, %1, 0xea;\n"
                     "add.f32 f0, %4, %12;\nadd.f32 f1, %5, %13;\ncvt.rn.bf16x2.f32 c1, f1, f0;\n"
                     "add.f32 f0, %6, %14;\nadd.f32 f1, %7, %15;\ncvt.rn.bf16x2.f32 c2, f1, f0;\n"
                     "add.f32 f0, %8, %16;\nadd.f32 f1, %9, %17;\ncvt.rn.bf16x2.f32 c3, f1, f0;\n"
                     "mov.b64 a, {c0, c1};\nmov.b64 b, {c2, c3};\nmov.b128 t, {a, b};\nst.relaxed.gpu.global.b128 [%0], t;\n}\n"
                     ::"l"(xo + 256 * u), "r"(par),
                     "f"(accP[8 * u]), "f"(accP[8 * u + 1]), "f"(accP[8 * u + 2]), "f"(accP[8 * u + 3]),
                     "f"(accP[8 * u + 4]), "f"(accP[8 * u + 5]), "f"(accP[8 * u + 6]), "f"(accP[8 * u + 7]),
                     "f"(sk[8 * u]), "f"(sk[8 * u + 1]), "f"(sk[8 * u + 2]), "f"(sk[8 * u + 3]),
                     "f"(sk[8 * u + 4]), "f"(sk[8 * u + 5]), "f"(sk[8 * u + 6]), "f"(sk[8 * u + 7]) : "memory");
      };
      const int ldat = w ? SOLO : LDAT;
      step(true);
      fence_acc(accP);
#pragma unroll 1
      for (int k = 2; k <= KL - ldat; k++) {
        step(k <= KL - 6);
        const bool park = w == 1 && k == KL - SOLO;
        const int lo = max(0, k - 2 - W1D * w), hi = park ? 4 : min(4, max(0, k - 1 - W1D * w));
#pragma unroll 1
        for (int u = lo; u < hi; u++) {
          if (u & 2) { if (u & 1) { send(6); send(7); } else { send(4); send(5); } }
          else { if (u & 1) { send(2); send(3); } else { send(0); send(1); } }
        }
        if (park) bar_sync(4, 256);
      }
#pragma unroll 1
      for (unsigned n = 0;; n++) {
        load_in();
#pragma unroll 1
        for (int k = n ? ldat : 0; k < ldat; k++) {
          if (w == 0 && k == LDAT - 1) bar_arrive(4, 256);
          step(false);
        }
        bool ok = true;
#pragma unroll
        for (int i = 0; i < 8; i++) ok = ok && (in[4 * i] & 1u) == par;
        if (__all_sync(0xffffffffu, ok)) break;
        if (n > SPIN_LIMIT) die();
      }
      const bool odd = q & 1;
      float* o0 = pin(p.out + (size_t)(128 * m + r0) * DM + 128 * j + (odd ? 8 + 2 * (q - 1) : 2 * q));
      wg_wait<0>();
      fence_acc(accO);
#pragma unroll
      for (int i = 0; i < 16; i += 2) {
#pragma unroll
        for (int h = 0; h < 2; h++) {
          const float p0 = h ? bf_lo(in[2 * i + 1]) : __uint_as_float(((in[2 * i] << 16) & 0xFFFE0000u) | 0x8000u);
          const float a0 = accO[4 * i + 2 * h] + p0, a1 = accO[4 * i + 2 * h + 1] + bf_hi(in[2 * i + h]);
          const float b0 = accO[4 * i + 4 + 2 * h] + bf_lo(in[2 * i + 2 + h]), b1 = accO[4 * i + 5 + 2 * h] + bf_hi(in[2 * i + 2 + h]);
          const float s0 = __shfl_xor_sync(0xffffffffu, odd ? a0 : b0, 1), s1 = __shfl_xor_sync(0xffffffffu, odd ? a1 : b1, 1);
          const float4 v = odd ? make_float4(s0, s1, b0, b1) : make_float4(a0, a1, s0, s1);
          *reinterpret_cast<float4*>(o0 + h * 32 * DM + 8 * i) = v;
        }
      }
    }
    asm volatile("barrier.cluster.arrive.relaxed.aligned;\nbarrier.cluster.wait.aligned;" ::: "memory");
  } else {
    asm volatile("setmaxnreg.dec.sync.aligned.u32 40;");
    if (__builtin_expect(warp > 0, 0)) {
      unsigned epoch;
      asm volatile("ld.volatile.global.u32 %0, [%1];" : "=r"(epoch) : "l"(&g_epoch[blockIdx.x]));
      auto gather_gate = [&](int mm, uint32_t dst) {
        unsigned long long v[4];
        unsigned n = 0;
        while (true) {
          bool ok = true;
#pragma unroll
          for (int i = 0; i < 4; i++)
            asm volatile("ld.relaxed.gpu.global.u64 %0, [%1];" : "=l"(v[i]) : "l"(&g_gate[128 * mm + 32 * i + lane]) : "memory");
#pragma unroll
          for (int i = 0; i < 4; i++) ok = ok && (unsigned)(v[i] >> 32) == epoch + 1;
          if (ok) break;
          __nanosleep(20);
          if (++n > SPIN_LIMIT) die();
        }
#pragma unroll
        for (int i = 0; i < 4; i++)
          asm volatile("st.shared.u16 [%0], %1;" ::"r"(dst + 80 * i + 2 * lane), "h"((unsigned short)((unsigned)v[i] >> 16)) : "memory");
      };
      auto publish = [&](int slab, int mm) {
        if (lane == 0) {
          asm volatile("fence.proxy.async.global;" ::: "memory");
          asm volatile("red.release.gpu.global.add.u32 [%0], %1;" ::"l"(&g_ready[(slab * 16 + mm) * 32]), "r"(slab == 4 ? 8 : 1) : "memory");
        }
        __syncwarp();
      };
      if (__builtin_expect(helper, 0)) {
        if (warp == 2) {
#pragma unroll 1
          for (int r = 0; r < 4; r++) gather_gate(m + 4 * r, sx + 320 * r);
          __syncwarp();
          if (lane == 0) asm volatile("mbarrier.arrive.shared::cta.b64 _, [%0];" ::"r"(rdy0 + 24) : "memory");
        } else if (warp == 1) {
#pragma unroll 1
          for (int r = 0; r < 4; r++) { bar_sync(1, 288); publish(4, m + 4 * r); }
          if (lane == 0) g_epoch[blockIdx.x] = epoch + 1;
        }
      } else {
    if (warp == 2) {
      {
        const uint2 dv = __ldg(reinterpret_cast<const uint2*>(p.dskip + 128 * (j ^ 1)) + lane);
        asm volatile("st.shared.v2.u32 [%0], {%1, %2};" ::"r"(sgate + 320 + 8 * lane), "r"(dv.x), "r"(dv.y) : "memory");
      }
      if (lane == 0) asm volatile("st.shared.u32 [%0], %1;" ::"r"(sgate + 576), "r"((epoch + 1) & 3u) : "memory");
      mbar_wait(rdy0 + 32, 0);
      gather_gate(m, sgate);
      __syncwarp();
      if (lane == 0) {
        asm volatile("mbarrier.arrive.shared::cta.b64 _, [%0];" ::"r"(rdy0 + 24) : "memory");
#pragma unroll 1
        for (int ph = 0; ph < (H ? 5 : 4); ph++) {
          const unsigned* c = &g_ready[(ph * 16 + m) * 32];
          unsigned v, n = 0;
          while (true) {
            asm volatile("ld.acquire.gpu.global.u32 %0, [%1];" : "=r"(v) : "l"(c) : "memory");
            if ((int)(v - (epoch + 1) * 8u) >= 0) break;
            __nanosleep(100);
            if (++n > SPIN_LIMIT) die();
          }
          asm volatile("mbarrier.arrive.shared::cta.b64 _, [%0];" ::"r"(rdy0 + (ph >= 3 ? 16 * ph : 8 * ph)) : "memory");
        }
        g_epoch[blockIdx.x] = epoch + 1;
      }
    } else if (__builtin_expect(warp == 3, 0)) {
      mbar_wait(rdy0 + 32, 0);
#pragma unroll 1
      for (int c = lane; c < 128; c += 32) {
        const float lr = __bfloat162float(p.lam_re[128 * j + c]), li = __bfloat162float(p.lam_im[128 * j + c]);
        const float dt = bfround(expf(__bfloat162float(p.log_dt[128 * j + c])));
        const float e = expf(dt * lr);
        const float ang = dt * li, th = ang * 0.318309873f;
        const float tl = fmaf(ang, 0.318309873f, -th) + ang * 1.28412765e-8f;
        const float tn = 2.f * rintf(0.5f * th);
        float sn, cs;
        sincospif((th - tn) + tl, &sn, &cs);
        cpx v = {e * cs, e * sn};
        const float nr = v.r - 1.f, inv = __fdividef(1.f, lr * lr + li * li);
        asm volatile("st.shared.v4.f32 [%0], {%1, %2, %3, %4};" ::"r"(stab + 16 * c), "f"(v.r), "f"(v.i),
                     "f"(2.f * ((nr * lr + v.i * li) * inv)), "f"(2.f * ((v.i * lr - nr * li) * inv)) : "memory");
      }
      __syncwarp();
      if (lane == 0) asm volatile("mbarrier.arrive.shared::cta.b64 _, [%0];" ::"r"(rdy0 + 40) : "memory");
    } else {
      {
#pragma unroll
        for (int i = 0; i < 4; i++)
          asm volatile("cp.async.cg.shared.global [%0], [%1], 16;" ::"r"(stab + i * 512 + lane * 16), "l"(p.gate_w + i * 256 + lane * 8) : "memory");
        const int R = 16 * j + (lane >> 1);
        float z0 = 0.f, z1 = 0.f;
#pragma unroll 1
        for (int k = 0; k < 16; k++) {
          mbar_wait(full0 + 8 * (k & 7), k >> 3);
          uint4 xv[4];
#pragma unroll
          for (int i = 0; i < 4; i++)
            asm volatile("ld.shared.v4.u32 {%0,%1,%2,%3}, [%4];" : "=r"(xv[i].x), "=r"(xv[i].y), "=r"(xv[i].z), "=r"(xv[i].w)
                         : "r"(sbase + (k & 3) * (3 * SLOT) + R * 128 + (((4 * (lane & 1) + i) ^ (R & 7)) << 4)) : "memory");
          __syncwarp();
          if (lane == 0) asm volatile("mbarrier.arrive.shared::cta.b64 _, [%0];" ::"r"(gdone + 8 * (k & 3)) : "memory");
          if (k == 0) { asm volatile("cp.async.wait_all;" ::: "memory"); __syncwarp(); }
#pragma unroll
          for (int i = 0; i < 4; i++) {
            uint4 gw;
            asm volatile("ld.shared.v4.u32 {%0,%1,%2,%3}, [%4];" : "=r"(gw.x), "=r"(gw.y), "=r"(gw.z), "=r"(gw.w)
                         : "r"(stab + 128 * k + 64 * (lane & 1) + 16 * i) : "memory");
            uint32_t u;
            u = mul_bf16x2(xv[i].x, gw.x); z0 += bf_lo(u); z1 += bf_hi(u);
            u = mul_bf16x2(xv[i].y, gw.y); z0 += bf_lo(u); z1 += bf_hi(u);
            u = mul_bf16x2(xv[i].z, gw.z); z0 += bf_lo(u); z1 += bf_hi(u);
            u = mul_bf16x2(xv[i].w, gw.w); z0 += bf_lo(u); z1 += bf_hi(u);
          }
        }
        z0 += z1;
        z0 += __shfl_xor_sync(0xffffffffu, z0, 1);
        z0 = bfround(__fdividef(1.f, 1.f + expf(-bfround(z0))));
        if (!(lane & 1)) {
          const unsigned long long v = ((unsigned long long)(epoch + 1) << 32) | __float_as_uint(z0);
          asm volatile("st.relaxed.gpu.global.u64 [%0], %1;" ::"l"(&g_gate[128 * m + R]), "l"(v) : "memory");
        }
        __syncwarp();
        if (lane == 0) asm volatile("mbarrier.arrive.shared::cta.b64 _, [%0];" ::"r"(rdy0 + 32) : "memory");
      }
#pragma unroll 1
      for (int ph = 0; ph < 4; ph++) {
        bar_sync(ph == 3 ? 8 : 1 + ph, ph < 2 ? 288 : 160);
        publish(ph, m);
      }
    }
      }
    } else {
      const int kh = j & 1, wcol = 128 * (j ^ rank);
      int s = 1;
      uint32_t a, b, fb;
      auto acquire = [&](int prev, uint32_t bytes) {
        if (prev >= 0) mbar_wait(empty0 + 8 * (prev & 7), (prev >> 3) & 1);
        fb = full0 + 8 * (s & 7);
        expect_tx(fb, bytes);
      };
      auto stage3 = [&](uint32_t bytes) {
        acquire(s - 4, bytes);
        a = sbase + (s & 3) * (3 * SLOT);
        b = a + SLOT * (1 + rank);
      };
      const CUtensorMap* bmap = rank ? &p.bim : &p.bre;
#pragma unroll 1
      for (; s < (helper ? 64 : 16); s++) {
        if (!helper && s >= 4) mbar_wait(gdone + 8 * (s & 3), ((s >> 2) - 1) & 1);
        stage3(bytes1);
        tma2(a, &p.x, fb, 64 * (s & 15), 128 * (m + 4 * (s >> 4)));
        tma3_mc(b, map1, fb, col1, 64 * (s & 15) + 32 * rank);
        if (s == 10) pf_map(&p.w1a);
      }
      if (!helper) {
#pragma unroll 1
      for (; s < 32; s++) {
        if (s < 20) mbar_wait(gdone + 8 * (s & 3), 1);
        stage3(SLOT + 2 * 12288);
        const bool keep = ((s - 16) >> 1) == (j ^ 1);
        tma2(keep ? sx + (s & 1) * SLOT : a, &p.x, fb, 64 * (s - 16), 128 * m);
        tma3_mc(b, &p.w1a, fb, 8 * NA + 192 * j, 64 * (s - 16) + 32 * rank);
        if (s == 26) { pf_map(&p.xp); pf_map(bmap); }
      }
#pragma unroll 1
      for (; s < 48; s++) {
        stage3(3 * SLOT);
        tma4(a, &p.xp, fb, 64 * (s - 32), 4 * m);
        tma2_mc(b, bmap, fb, 64 * (s - 32), 128 * j);
        if (s == 42) { pf_map(&p.hf); pf_map(&p.w2); }
      }
      mbar_wait(rdy0, 0);
      auto wideF = [&](int kb) {
        stage3(3 * SLOT);
        tma2(a, &p.hf, fb, 64 * kb, 128 * m);
        tma5_mc(b, &p.w2, fb, wcol, 2 * kb);
        tma5_mc(b + 8192, &p.w2, fb, wcol + 64, 2 * kb);
      };
      int kb = BA * kh;
#pragma unroll 1
      for (; s < SF; s++, kb++) {
        if (s == 48 + BA) { mbar_wait(rdy0 + 8, 0); kb = 2 * BA + 12 * kh; pf_map(&p.hs); pf_map(&p.cre); pf_map(&p.cim); }
        wideF(kb);
      }
      mbar_wait(rdy0 + 16, 0);
      auto ssm_k = [](int i) { return i < 8 ? 128 * i : 128 * (i - 8) + 64; };
      const CUtensorMap* cmap = kh ? &p.cim : &p.cre;
#pragma unroll 1
      for (; s < SF + KW; s++) {
        if (s == SF + 8) { mbar_wait(rdy0 + 48, 0); pf_map(&p.cre); pf_map(&p.cim); pf_map(&p.hf); pf_map(&p.w2); }
        stage3(3 * SLOT);
        const int k0 = ssm_k(s - SF);
        tma3(a, &p.hs, fb, 1024 * kh + k0, 2 * m);
        tma2_mc(b, cmap, fb, k0, wcol);
        tma2_mc(b + 8192, cmap, fb, k0, wcol + 64);
      }
      if (H) {
        mbar_wait(rdy0 + 64, 0);
#pragma unroll 1
        for (int i = 0; i < NC; i++, s++) wideF(52 + NC * kh + i);
      }
      auto narrow = [&](int l) {
        const int im = l >= KL / 2, k0 = ssm_k(KW + l - im * (KL / 2));
        tma3(a, &p.hs, fb, 1024 * im + k0, 2 * m);
        tma2_mc(a + SLOT + rank * 8192, im ? &p.cim : &p.cre, fb, k0, 128 * j + 64 * rank);
      };
      uint32_t a2 = sbase + ((S3 & 3) * 3 / 2) * (2 * SLOT);
#pragma unroll 1
      for (int i = 0; i < KL; i++) {
        int l = i - (i > XTRA);
        if (i == XTRA) {
          l = KL - 1; a = sx; fb = rdy0 + 56;
          expect_tx(fb, 2 * SLOT);
        } else {
          acquire(l < 6 ? S3 - 4 + ((0x332110 >> (4 * l)) & 3) : s - 6, 2 * SLOT);
          a = a2;
          a2 += 2 * SLOT;
          if (a2 == sbase + RING) a2 = sbase;
          s++;
        }
        narrow(l);
      }
      }
    }
    __syncwarp();
    asm volatile("barrier.cluster.arrive.relaxed.aligned;\nbarrier.cluster.wait.aligned;" ::: "memory");
  }
}

__global__ void __launch_bounds__(384, 1) probe_kernel() {}

typedef CUresult (*EncodeFn)(CUtensorMap*, CUtensorMapDataType, cuuint32_t, void*, const cuuint64_t*, const cuuint64_t*,
                             const cuuint32_t*, const cuuint32_t*, CUtensorMapInterleave, CUtensorMapSwizzle,
                             CUtensorMapL2promotion, CUtensorMapFloatOOBfill);

void make_map(EncodeFn enc, CUtensorMap* tm, const void* ptr, int rank, const cuuint64_t* dims, const cuuint64_t* strides,
              const cuuint32_t* box, CUtensorMapSwizzle swz = CU_TENSOR_MAP_SWIZZLE_128B) {
  const cuuint32_t es[5] = {1, 1, 1, 1, 1};
  enc(tm, CU_TENSOR_MAP_DATA_TYPE_BFLOAT16, rank, const_cast<void*>(ptr), dims, strides, box, es,
      CU_TENSOR_MAP_INTERLEAVE_NONE, swz, CU_TENSOR_MAP_L2_PROMOTION_L2_256B,
      CU_TENSOR_MAP_FLOAT_OOB_FILL_NONE);
}

}

extern "C" void kernel_launch(void* const* d_in, const int* in_sizes, int n_in, void* d_out, int out_size) {
  (void)in_sizes; (void)n_in; (void)out_size;
  typedef const __nv_bfloat16* bp;
  bp x = (bp)d_in[0], lam_re = (bp)d_in[1], lam_im = (bp)d_in[2], b_re = (bp)d_in[3], b_im = (bp)d_in[4];
  bp c_re = (bp)d_in[5], c_im = (bp)d_in[6], log_dt = (bp)d_in[7], dskip = (bp)d_in[8];
  bp w1 = (bp)d_in[10], w2 = (bp)d_in[11], gate_w = (bp)d_in[12];

  void* fn = nullptr;
  cudaDriverEntryPointQueryResult qres;
  cudaGetDriverEntryPoint("cuTensorMapEncodeTiled", &fn, cudaEnableDefault, &qres);
  EncodeFn enc = (EncodeFn)fn;
  void *hs = nullptr, *hf = nullptr;
  cudaGetSymbolAddress(&hs, g_Hs);
  cudaGetSymbolAddress(&hf, g_Hf);

  Params p = {};
  { cuuint64_t d[4] = {1024, 2, 64, 16}, s[3] = {2048, 32 * 2048, 2 * 2048}; cuuint32_t b[4] = {64, 2, 4, 16}; make_map(enc, &p.xp, x, 4, d, s, b); }
  { cuuint64_t d[2] = {1024, 2048}, s[1] = {2048}; cuuint32_t b[2] = {64, 128}; make_map(enc, &p.x, x, 2, d, s, b); }
  { cuuint64_t d[2] = {1024, 1024}, s[1] = {2048}; cuuint32_t b[2] = {64, 128};
    make_map(enc, &p.bre, b_re, 2, d, s, b); make_map(enc, &p.bim, b_im, 2, d, s, b); }
  { cuuint64_t d[3] = {3584, 1024, 4}, s[2] = {3584 * 2, 128}; cuuint32_t ba[3] = {64, 32, 3}, bb[3] = {64, 32, 4};
    make_map(enc, &p.w1a, w1, 3, d, s, ba); make_map(enc, &p.w1b, w1, 3, d, s, bb); }
  { cuuint64_t d[3] = {3584, 1024, 7}, s[2] = {3584 * 2, 64}; cuuint32_t b[3] = {32, 32, 7};
    make_map(enc, &p.w1c, w1, 3, d, s, b, CU_TENSOR_MAP_SWIZZLE_64B); }
  { cuuint64_t d[3] = {64, 2048, 32}, s[2] = {4096, 128}; cuuint32_t b[3] = {64, 64, 2}; make_map(enc, &p.hs, hs, 3, d, s, b); }
  { cuuint64_t d[2] = {3584, 2048}, s[1] = {3584 * 2}; cuuint32_t b[2] = {64, 128}; make_map(enc, &p.hf, hf, 2, d, s, b); }
  { cuuint64_t d[2] = {1024, 1024}, s[1] = {2048}; cuuint32_t b[2] = {64, 64};
    make_map(enc, &p.cre, c_re, 2, d, s, b); make_map(enc, &p.cim, c_im, 2, d, s, b); }
  { cuuint64_t d[5] = {1024, 2, 4, 4, 112}, s[4] = {2048, 8 * 2048, 2 * 2048, 32 * 2048}; cuuint32_t b[5] = {64, 2, 4, 4, 2};
    make_map(enc, &p.w2, w2, 5, d, s, b); }
  p.lam_re = lam_re; p.lam_im = lam_im; p.log_dt = log_dt; p.dskip = dskip; p.gate_w = gate_w;
  p.out = (float*)d_out;

  cudaFuncSetAttribute(fused_kernel<true>, cudaFuncAttributeMaxDynamicSharedMemorySize, SMEM_BYTES);
  cudaFuncSetAttribute(fused_kernel<false>, cudaFuncAttributeMaxDynamicSharedMemorySize, SMEM_BYTES);
  cudaFuncSetAttribute(probe_kernel, cudaFuncAttributeMaxDynamicSharedMemorySize, SMEM_BYTES);
  cudaLaunchConfig_t cfg = {};
  cfg.gridDim = dim3(132); cfg.blockDim = dim3(384); cfg.dynamicSmemBytes = SMEM_BYTES;
  cudaLaunchAttribute at[1];
  at[0].id = cudaLaunchAttributeClusterDimension;
  at[0].val.clusterDim.x = 2; at[0].val.clusterDim.y = 1; at[0].val.clusterDim.z = 1;
  cfg.attrs = at; cfg.numAttrs = 1;
  auto max_clusters = [&](int size) {
    int n = 0;
    at[0].val.clusterDim.x = size;
    cfg.gridDim = dim3(16 * size);
    if (cudaOccupancyMaxActiveClusters(&n, probe_kernel, &cfg) != cudaSuccess) { n = 0; (void)cudaGetLastError(); }
    return n;
  };
  const bool useh = USEH && max_clusters(2) >= 66;
  for (int c = 0; c < 66; c++) p.tile[c] = c >= 64 ? c : ((((c >> 5) << 2) | ((c >> 1) & 3)) << 3) | ((c & 1) << 2) | ((c >> 3) & 3);
  if (max_clusters(2) == 66 && max_clusters(4) == 30 && max_clusters(8) == 15) {
    for (int i = 0; i < 4; i++) p.tile[i] = 4 + i;
    for (int c = 0; c < 32; c++) p.tile[4 + c] = 8 * (c & 7) + (c >> 3);
    for (int c = 0; c < 28; c++) p.tile[36 + c] = 8 * (c % 7) + 12 + c / 7;
  }
  if (useh) fused_kernel<true><<<132, 384, SMEM_BYTES>>>(p);
  else fused_kernel<false><<<128, 384, SMEM_BYTES>>>(p);
}
```
